```python
import torch

def _softmax(x, axis=-1):
    return torch.softmax(x, dim=axis)
def _gelu(x):
    return torch.nn.functional.gelu(x, approximate="tanh")
def _silu(x):
    return torch.nn.functional.silu(x)
def _sigmoid(x):
    return torch.sigmoid(x)
def _layernorm(x, axis=-1, eps=1e-5):
    m = x.mean(dim=axis, keepdim=True)
    v = x.var(dim=axis, keepdim=True, unbiased=False)
    return (x - m) / torch.sqrt(v + eps)
def _scatter_add(tgt, idx, src, axis=0):
    return tgt.clone().index_add_(axis, idx, src)
def _segment_sum(src, seg, n):
    out = torch.zeros((n,) + src.shape[1:], dtype=src.dtype)
    return out.index_add_(0, seg, src)
def _pad(x, pw):
    flat = tuple(v for pair in reversed(pw) for v in pair)
    return torch.nn.functional.pad(x, flat)

kernel_name = 'interleave_layers__linear_attn_block__dense_activation_relu__prompt'

def setup_inputs():

    _w = (lambda a: (lambda t: t.to(torch.bfloat16) if t.is_floating_point() else t)(torch.as_tensor(a)))
    def _A_setup():
        B, S, D = 1, 2048, 512
        return {
            "x": _w((lambda *s: torch.randn(*s, dtype=torch.bfloat16) * 0.05)(B, S, D)),
            "wqkv": _w((lambda *s: torch.randn(*s, dtype=torch.bfloat16) * 0.1)(D, 3 * D)),
            "wo": _w((lambda *s: torch.randn(*s, dtype=torch.bfloat16) * 0.05)(D, D)),
        }
    _A_in = _A_setup()

    def _B_setup():
        B, S, D, Dff = 1, 2048, 512, 1376
        return {
            "x": _w((lambda *s: torch.randn(*s, dtype=torch.bfloat16) * 0.05)(B, S, D)),
            "w1": _w((lambda *s: torch.randn(*s, dtype=torch.bfloat16) * 0.05)(D, Dff)),
            "w2": _w((lambda *s: torch.randn(*s, dtype=torch.bfloat16) * 0.05)(Dff, D)),
        }
    _B_in = _B_setup()

    return {
        "A_x": _A_in["x"],
        "A_wqkv": _A_in["wqkv"],
        "A_wo": _A_in["wo"],
        "B_x": _B_in["x"],
        "B_w1": _B_in["w1"],
        "B_w2": _B_in["w2"],
    }

def reference(A_x, A_wqkv, A_wo, B_x, B_w1, B_w2):
    def _A_ref(x, wqkv, wo):
        B, S, D = x.shape
        H = 32; Dh = D // H
        qkv = (lambda x, *d: x.permute(*d))((x @ wqkv).reshape(B, S, 3, H, Dh), 2, 0, 3, 1, 4)
        q, k, v = qkv[0], qkv[1], qkv[2]
        phi = lambda t: torch.where(t > 0, t + 1, torch.exp(t)) + 1e-6
        pq, pk = phi(q), phi(k)
        kv = torch.einsum("bhsd,bhse->bhde", pk, v)
        z = torch.einsum("bhsd->bhd", pk)
        num = torch.einsum("bhqd,bhde->bhqe", pq, kv)
        den = torch.einsum("bhqd,bhd->bhq", pq, z)[..., None] + 1e-6
        o = num / den
        return (lambda x, *d: x.permute(*d))(o, 0, 2, 1, 3).reshape(B, S, D) @ wo

    def _B_ref(x, w1, w2):
        h = torch.einsum("bsd,df->bsf", x, w1)
        zero = torch.zeros_like(h)
        h = torch.maximum(h, zero)
        return torch.einsum("bsf,fd->bsd", h, w2)

    x = A_x
    x = x + _A_ref(_layernorm(x, axis=-1), A_wqkv, A_wo)
    x = x + _B_ref(_layernorm(x, axis=-1), B_w1, B_w2)
    x = x + _A_ref(_layernorm(x, axis=-1), A_wqkv, A_wo)
    x = x + _B_ref(_layernorm(x, axis=-1), B_w1, B_w2)
    return x
```

```cpp
#include <cuda_runtime.h>
#include <cuda_bf16.h>
#include <cuda.h>
#include <stdint.h>

#define TS_ENABLE 0

#define W1_DELAY 100
#define STAGGER 200
#define H_STAGGER 300
#define SRC_DELAY 100
#define O_DELAY 100
#define O_STAGGER 100
#define POLL_GAP 250

namespace {

constexpr int RING = 5;
constexpr uint32_t SM_A = RING * 16384;
constexpr uint32_t SM_STG = SM_A + 8 * 16384;
constexpr uint32_t SM_ONES = SM_STG + 16384;
constexpr uint32_t SM_BAR = SM_ONES + 2048;
constexpr uint32_t SM_CS = SM_BAR + 528;
constexpr uint32_t SMEM_BYTES = SM_CS + 448;
constexpr uint32_t SPIN_LIMIT = 4000000;

__device__ uint4 g_xa[16 * 2 * 8 * 512];
__device__ float4 g_cs[8 * 144];
__device__ uint4 g_st[16 * 2 * 8 * 32];
__device__ uint4 g_oa[16 * 2 * 8 * 512];
__device__ uint32_t g_xh[16 * 2 * 32];
__device__ uint32_t g_oh[16 * 2 * 32];
__device__ uint4 g_h[16 * 2 * 88 * 128];
__device__ uint32_t g_hf[16 * 2 * 2 * 32];
__device__ float4 g_fix[256 * 2048];
__device__ float4 g_kv[2 * 8 * 3 * 128];
#define TS(i) do {} while (0)
#define TSW(r, i) do {} while (0)
#define TSG(i) do {} while (0)

__device__ __forceinline__ void mbar_init(uint32_t bar, int cnt) { asm volatile("mbarrier.init.shared::cta.b64 [%0], %1;" :: "r"(bar), "r"(cnt)); }
__device__ __forceinline__ void mbar_expect_tx(uint32_t bar, uint32_t bytes) { asm volatile("mbarrier.arrive.expect_tx.shared::cta.b64 _, [%0], %1;" :: "r"(bar), "r"(bytes) : "memory"); }
__device__ __forceinline__ void mbar_arrive(uint32_t bar) { asm volatile("mbarrier.arrive.shared::cta.b64 _, [%0];" :: "r"(bar) : "memory"); }
__device__ __forceinline__ void mbar_wait(uint32_t bar, uint32_t parity) {
    asm volatile("{\n .reg .pred p;\n LAB_WAIT:\n mbarrier.try_wait.parity.shared::cta.b64 p, [%0], %1;\n @!p bra LAB_WAIT;\n }" :: "r"(bar), "r"(parity) : "memory");
}
__device__ __forceinline__ void mbar_wait_bounded(uint32_t bar, uint32_t parity) {
    asm volatile("{\n .reg .pred p;\n .reg .u32 c;\n mov.u32 c, 0;\n"
                 "LAB_WAIT:\n mbarrier.try_wait.parity.shared::cta.b64 p, [%0], %1;\n @p bra DONE;\n add.u32 c, c, 1;\n"
                 " setp.lt.u32 p, c, 4000000;\n @p bra LAB_WAIT;\n trap;\n DONE:\n }" :: "r"(bar), "r"(parity) : "memory");
}
__device__ __forceinline__ void mbar_wait2(uint32_t b0, uint32_t p0, uint32_t b1, uint32_t p1) {
    asm volatile("{ .reg .pred p, q;\n LAB_WAIT:\n mbarrier.try_wait.parity.shared::cta.b64 p, [%0], %1;\n mbarrier.try_wait.parity.shared::cta.b64 q, [%2], %3;\n"
                 " and.pred p, p, q;\n @!p bra LAB_WAIT;\n }" :: "r"(b0), "r"(p0), "r"(b1), "r"(p1) : "memory");
}
__device__ __forceinline__ bool elect_one() { uint32_t p; asm volatile("{ .reg .pred P; elect.sync _|P, 0xffffffff; selp.u32 %0, 1, 0, P; }" : "=r"(p)); return p != 0; }
__device__ __forceinline__ void tma2d(uint32_t dst, const CUtensorMap* m, int c0, int c1, uint32_t bar) {
    asm volatile("cp.async.bulk.tensor.2d.shared::cluster.global.mbarrier::complete_tx::bytes [%0], [%1, {%2, %3}], [%4];"
                 :: "r"(dst), "l"(m), "r"(c0), "r"(c1), "r"(bar) : "memory");
}
__device__ __forceinline__ void bulk1d(uint32_t dst, const void* src, uint32_t bytes, uint32_t bar) {
    asm volatile("cp.async.bulk.shared::cluster.global.mbarrier::complete_tx::bytes [%0], [%1], %2, [%3];" :: "r"(dst), "l"(src), "r"(bytes), "r"(bar) : "memory");
}
__device__ __forceinline__ void l2_prefetch(const void* src, uint32_t bytes) { asm volatile("cp.async.bulk.prefetch.L2.global [%0], %1;" :: "l"(src), "r"(bytes) : "memory"); }
__device__ __forceinline__ void wg_fence() { asm volatile("wgmma.fence.sync.aligned;" ::: "memory"); }
__device__ __forceinline__ void wg_commit() { asm volatile("wgmma.commit_group.sync.aligned;" ::: "memory"); }
template <int N> __device__ __forceinline__ void wg_wait() { asm volatile("wgmma.wait_group.sync.aligned %0;" :: "n"(N) : "memory"); }
__device__ __forceinline__ void bar_sync(int id, int n) { asm volatile("bar.sync %0, %1;" :: "r"(id), "r"(n) : "memory"); }
__device__ __forceinline__ void sts128(uint32_t a, uint4 v) { asm volatile("st.shared.v4.u32 [%0], {%1,%2,%3,%4};" :: "r"(a), "r"(v.x), "r"(v.y), "r"(v.z), "r"(v.w) : "memory"); }
__device__ __forceinline__ uint4 ldsm4(uint32_t a) { uint4 v; asm volatile("ldmatrix.sync.aligned.m8n8.x4.shared.b16 {%0,%1,%2,%3}, [%4];" : "=r"(v.x), "=r"(v.y), "=r"(v.z), "=r"(v.w) : "r"(a) : "memory"); return v; }
__device__ __forceinline__ uint4 ldsm4t(uint32_t a) { uint4 v; asm volatile("ldmatrix.sync.aligned.m8n8.x4.trans.shared.b16 {%0,%1,%2,%3}, [%4];" : "=r"(v.x), "=r"(v.y), "=r"(v.z), "=r"(v.w) : "r"(a) : "memory"); return v; }
__device__ __forceinline__ void stsm4(uint32_t a, uint4 v) { asm volatile("stmatrix.sync.aligned.m8n8.x4.shared.b16 [%0], {%1,%2,%3,%4};" :: "r"(a), "r"(v.x), "r"(v.y), "r"(v.z), "r"(v.w) : "memory"); }
__device__ __forceinline__ uint4 ld_strong(const void* p) { uint4 v; asm volatile("ld.relaxed.gpu.global.v4.u32 {%0,%1,%2,%3}, [%4];" : "=r"(v.x), "=r"(v.y), "=r"(v.z), "=r"(v.w) : "l"(p) : "memory"); return v; }
__device__ __forceinline__ uint32_t ld_strong32(const void* p) { uint32_t v; asm volatile("ld.relaxed.gpu.global.u32 %0, [%1];" : "=r"(v) : "l"(p) : "memory"); return v; }
__device__ __forceinline__ void spin(uint32_t n) { uint32_t t0, t; asm volatile("mov.u32 %0, %%clock;" : "=r"(t0)); do { asm volatile("mov.u32 %0, %%clock;" : "=r"(t)); } while (t - t0 < n); }
__device__ __forceinline__ void st_strong(void* p, uint4 v) { asm volatile("st.relaxed.gpu.global.v4.u32 [%0], {%1,%2,%3,%4};" :: "l"(p), "r"(v.x), "r"(v.y), "r"(v.z), "r"(v.w) : "memory"); }
__device__ __forceinline__ void red_add4(void* p, float a, float b, float c, float d) { asm volatile("red.relaxed.gpu.global.add.v4.f32 [%0], {%1,%2,%3,%4};" :: "l"(p), "f"(a), "f"(b), "f"(c), "f"(d) : "memory"); }
__device__ __forceinline__ uint32_t pack_bf16(float lo, float hi) { uint32_t r; asm("cvt.rn.bf16x2.f32 %0, %1, %2;" : "=r"(r) : "f"(hi), "f"(lo)); return r; }
__device__ __forceinline__ void mma16816(float (&d)[4], const uint4& a, uint32_t b0, uint32_t b1) {
    asm volatile("mma.sync.aligned.m16n8k16.row.col.f32.bf16.bf16.f32 {%0,%1,%2,%3}, {%4,%5,%6,%7}, {%8,%9}, {%10,%10,%10,%10};"
                 : "=f"(d[0]), "=f"(d[1]), "=f"(d[2]), "=f"(d[3]) : "r"(a.x), "r"(a.y), "r"(a.z), "r"(a.w), "r"(b0), "r"(b1), "f"(0.f));
}
__device__ __forceinline__ void mma16816_acc(float (&d)[4], const uint4& a, uint32_t b0, uint32_t b1) {
    asm volatile("mma.sync.aligned.m16n8k16.row.col.f32.bf16.bf16.f32 {%0,%1,%2,%3}, {%4,%5,%6,%7}, {%8,%9}, {%0,%1,%2,%3};"
                 : "+f"(d[0]), "+f"(d[1]), "+f"(d[2]), "+f"(d[3]) : "r"(a.x), "r"(a.y), "r"(a.z), "r"(a.w), "r"(b0), "r"(b1));
}
__device__ __forceinline__ uint32_t mkdesc(uint32_t addr) { return ((addr & 0x3FFFF) >> 4) | ((8192u >> 4) << 16); }
__device__ __forceinline__ float sel4(int i, float a, float b, float c, float d) {
    float r;
    asm("{ .reg .pred p, q; .reg .f32 x, y; .reg .b32 t;\n and.b32 t, %1, 1; setp.ne.b32 p, t, 0; and.b32 t, %1, 2; setp.ne.b32 q, t, 0;\n"
        " selp.f32 x, %3, %2, p; selp.f32 y, %5, %4, p; selp.f32 %0, y, x, q; }" : "=f"(r) : "r"(i), "f"(a), "f"(b), "f"(c), "f"(d));
    return r;
}
__device__ __forceinline__ float phi(float a, float r, float rl) {
    const float n = fminf(a, 0.f);
    float e; asm("ex2.approx.ftz.f32 %0, %1;" : "=f"(e) : "f"(n * rl));
    return fmaf(a - n, r, e + 1e-6f);
}
__device__ __forceinline__ float rcp(float x) { float r; asm("rcp.approx.ftz.f32 %0, %1;" : "=f"(r) : "f"(x)); return r; }
__device__ __forceinline__ uint32_t mkdesc_a(uint32_t addr) { return ((addr & 0x3FFFF) >> 4) | ((1024u >> 4) << 16); }

__device__ __forceinline__ void wgmma_n48(float (&d)[24], uint32_t descA, uint32_t hiA, uint32_t descB, int scaleD) {
    asm volatile("{\n.reg .pred p;\n.reg .b64 da, db;\nsetp.ne.b32 p, %27, 0;\nmov.b64 da, {%24, %25};\nmov.b64 db, {%26, 0x40000040};\n"
        "wgmma.mma_async.sync.aligned.m64n48k16.f32.bf16.bf16 "
        "{%0, %1, %2, %3, %4, %5, %6, %7, %8, %9, %10, %11, %12, %13, %14, %15, %16, %17, %18, %19, %20, %21, %22, %23}, "
        "da, db, p, 1, 1, 0, 1;\n}\n"
        : "+f"(d[0]), "+f"(d[1]), "+f"(d[2]), "+f"(d[3]), "+f"(d[4]), "+f"(d[5]), "+f"(d[6]), "+f"(d[7]), "+f"(d[8]), "+f"(d[9]), "+f"(d[10]), "+f"(d[11]), "+f"(d[12]), "+f"(d[13]), "+f"(d[14]), "+f"(d[15]), "+f"(d[16]), "+f"(d[17]), "+f"(d[18]), "+f"(d[19]), "+f"(d[20]), "+f"(d[21]), "+f"(d[22]), "+f"(d[23])
        : "r"(descA), "r"(hiA), "r"(descB), "r"(scaleD));
}
__device__ __forceinline__ void wgmma_n64(float (&d)[32], uint32_t descA, uint32_t hiA, uint32_t descB, int scaleD) {
    asm volatile("{\n.reg .pred p;\n.reg .b64 da, db;\nsetp.ne.b32 p, %35, 0;\nmov.b64 da, {%32, %33};\nmov.b64 db, {%34, 0x40000040};\n"
        "wgmma.mma_async.sync.aligned.m64n64k16.f32.bf16.bf16 "
        "{%0, %1, %2, %3, %4, %5, %6, %7, %8, %9, %10, %11, %12, %13, %14, %15, %16, %17, %18, %19, %20, %21, %22, %23, %24, %25, %26, %27, %28, %29, %30, %31}, "
        "da, db, p, 1, 1, 0, 1;\n}\n"
        : "+f"(d[0]), "+f"(d[1]), "+f"(d[2]), "+f"(d[3]), "+f"(d[4]), "+f"(d[5]), "+f"(d[6]), "+f"(d[7]), "+f"(d[8]), "+f"(d[9]), "+f"(d[10]), "+f"(d[11]), "+f"(d[12]), "+f"(d[13]), "+f"(d[14]), "+f"(d[15]), "+f"(d[16]), "+f"(d[17]), "+f"(d[18]), "+f"(d[19]), "+f"(d[20]), "+f"(d[21]), "+f"(d[22]), "+f"(d[23]), "+f"(d[24]), "+f"(d[25]), "+f"(d[26]), "+f"(d[27]), "+f"(d[28]), "+f"(d[29]), "+f"(d[30]), "+f"(d[31])
        : "r"(descA), "r"(hiA), "r"(descB), "r"(scaleD));
}
__device__ __forceinline__ void wgmma_n128(float (&d)[64], uint32_t descA, uint32_t hiA, uint32_t descB, int scaleD) {
    asm volatile("{\n.reg .pred p;\n.reg .b64 da, db;\nsetp.ne.b32 p, %67, 0;\nmov.b64 da, {%64, %65};\nmov.b64 db, {%66, 0x40000040};\n"
        "wgmma.mma_async.sync.aligned.m64n128k16.f32.bf16.bf16 "
        "{%0, %1, %2, %3, %4, %5, %6, %7, %8, %9, %10, %11, %12, %13, %14, %15, %16, %17, %18, %19, %20, %21, %22, %23, %24, %25, %26, %27, %28, %29, %30, %31, %32, %33, %34, %35, %36, %37, %38, %39, %40, %41, %42, %43, %44, %45, %46, %47, %48, %49, %50, %51, %52, %53, %54, %55, %56, %57, %58, %59, %60, %61, %62, %63}, "
        "da, db, p, 1, 1, 0, 1;\n}\n"
        : "+f"(d[0]), "+f"(d[1]), "+f"(d[2]), "+f"(d[3]), "+f"(d[4]), "+f"(d[5]), "+f"(d[6]), "+f"(d[7]), "+f"(d[8]), "+f"(d[9]), "+f"(d[10]), "+f"(d[11]), "+f"(d[12]), "+f"(d[13]), "+f"(d[14]), "+f"(d[15]), "+f"(d[16]), "+f"(d[17]), "+f"(d[18]), "+f"(d[19]), "+f"(d[20]), "+f"(d[21]), "+f"(d[22]), "+f"(d[23]), "+f"(d[24]), "+f"(d[25]), "+f"(d[26]), "+f"(d[27]), "+f"(d[28]), "+f"(d[29]), "+f"(d[30]), "+f"(d[31]), "+f"(d[32]), "+f"(d[33]), "+f"(d[34]), "+f"(d[35]), "+f"(d[36]), "+f"(d[37]), "+f"(d[38]), "+f"(d[39]), "+f"(d[40]), "+f"(d[41]), "+f"(d[42]), "+f"(d[43]), "+f"(d[44]), "+f"(d[45]), "+f"(d[46]), "+f"(d[47]), "+f"(d[48]), "+f"(d[49]), "+f"(d[50]), "+f"(d[51]), "+f"(d[52]), "+f"(d[53]), "+f"(d[54]), "+f"(d[55]), "+f"(d[56]), "+f"(d[57]), "+f"(d[58]), "+f"(d[59]), "+f"(d[60]), "+f"(d[61]), "+f"(d[62]), "+f"(d[63])
        : "r"(descA), "r"(hiA), "r"(descB), "r"(scaleD));
}
__device__ __forceinline__ void wgmma_rs_n72(float (&d)[36], const uint4& a, uint32_t descB, int scaleD) {
    asm volatile("{\n.reg .pred p;\n.reg .b64 db;\nsetp.ne.b32 p, %41, 0;\nmov.b64 db, {%40, 0x40000040};\n"
        "wgmma.mma_async.sync.aligned.m64n72k16.f32.bf16.bf16 "
        "{%0, %1, %2, %3, %4, %5, %6, %7, %8, %9, %10, %11, %12, %13, %14, %15, %16, %17, %18, %19, %20, %21, %22, %23, %24, %25, %26, %27, %28, %29, %30, %31, %32, %33, %34, %35}, "
        "{%36, %37, %38, %39}, db, p, 1, 1, 1;\n}\n"
        : "+f"(d[0]), "+f"(d[1]), "+f"(d[2]), "+f"(d[3]), "+f"(d[4]), "+f"(d[5]), "+f"(d[6]), "+f"(d[7]), "+f"(d[8]), "+f"(d[9]), "+f"(d[10]), "+f"(d[11]), "+f"(d[12]), "+f"(d[13]), "+f"(d[14]), "+f"(d[15]), "+f"(d[16]), "+f"(d[17]), "+f"(d[18]), "+f"(d[19]), "+f"(d[20]), "+f"(d[21]), "+f"(d[22]), "+f"(d[23]), "+f"(d[24]), "+f"(d[25]), "+f"(d[26]), "+f"(d[27]), "+f"(d[28]), "+f"(d[29]), "+f"(d[30]), "+f"(d[31]), "+f"(d[32]), "+f"(d[33]), "+f"(d[34]), "+f"(d[35])
        : "r"(a.x), "r"(a.y), "r"(a.z), "r"(a.w), "r"(descB), "r"(scaleD));
}
__device__ __forceinline__ void wgmma_rs_n64(float (&d)[32], const uint4& a, uint32_t descB, int scaleD) {
    asm volatile("{\n.reg .pred p;\n.reg .b64 db;\nsetp.ne.b32 p, %37, 0;\nmov.b64 db, {%36, 0x40000040};\n"
        "wgmma.mma_async.sync.aligned.m64n64k16.f32.bf16.bf16 "
        "{%0, %1, %2, %3, %4, %5, %6, %7, %8, %9, %10, %11, %12, %13, %14, %15, %16, %17, %18, %19, %20, %21, %22, %23, %24, %25, %26, %27, %28, %29, %30, %31}, "
        "{%32, %33, %34, %35}, db, p, 1, 1, 1;\n}\n"
        : "+f"(d[0]), "+f"(d[1]), "+f"(d[2]), "+f"(d[3]), "+f"(d[4]), "+f"(d[5]), "+f"(d[6]), "+f"(d[7]), "+f"(d[8]), "+f"(d[9]), "+f"(d[10]), "+f"(d[11]), "+f"(d[12]), "+f"(d[13]), "+f"(d[14]), "+f"(d[15]), "+f"(d[16]), "+f"(d[17]), "+f"(d[18]), "+f"(d[19]), "+f"(d[20]), "+f"(d[21]), "+f"(d[22]), "+f"(d[23]), "+f"(d[24]), "+f"(d[25]), "+f"(d[26]), "+f"(d[27]), "+f"(d[28]), "+f"(d[29]), "+f"(d[30]), "+f"(d[31])
        : "r"(a.x), "r"(a.y), "r"(a.z), "r"(a.w), "r"(descB), "r"(scaleD));
}
__device__ __forceinline__ void wgmma_rs_n128(float (&d)[64], const uint4& a, uint32_t descB, int scaleD) {
    asm volatile("{\n.reg .pred p;\n.reg .b64 db;\nsetp.ne.b32 p, %69, 0;\nmov.b64 db, {%68, 0x40000040};\n"
        "wgmma.mma_async.sync.aligned.m64n128k16.f32.bf16.bf16 "
        "{%0, %1, %2, %3, %4, %5, %6, %7, %8, %9, %10, %11, %12, %13, %14, %15, %16, %17, %18, %19, %20, %21, %22, %23, %24, %25, %26, %27, %28, %29, %30, %31, %32, %33, %34, %35, %36, %37, %38, %39, %40, %41, %42, %43, %44, %45, %46, %47, %48, %49, %50, %51, %52, %53, %54, %55, %56, %57, %58, %59, %60, %61, %62, %63}, "
        "{%64, %65, %66, %67}, db, p, 1, 1, 1;\n}\n"
        : "+f"(d[0]), "+f"(d[1]), "+f"(d[2]), "+f"(d[3]), "+f"(d[4]), "+f"(d[5]), "+f"(d[6]), "+f"(d[7]), "+f"(d[8]), "+f"(d[9]), "+f"(d[10]), "+f"(d[11]), "+f"(d[12]), "+f"(d[13]), "+f"(d[14]), "+f"(d[15]), "+f"(d[16]), "+f"(d[17]), "+f"(d[18]), "+f"(d[19]), "+f"(d[20]), "+f"(d[21]), "+f"(d[22]), "+f"(d[23]), "+f"(d[24]), "+f"(d[25]), "+f"(d[26]), "+f"(d[27]), "+f"(d[28]), "+f"(d[29]), "+f"(d[30]), "+f"(d[31]), "+f"(d[32]), "+f"(d[33]), "+f"(d[34]), "+f"(d[35]), "+f"(d[36]), "+f"(d[37]), "+f"(d[38]), "+f"(d[39]), "+f"(d[40]), "+f"(d[41]), "+f"(d[42]), "+f"(d[43]), "+f"(d[44]), "+f"(d[45]), "+f"(d[46]), "+f"(d[47]), "+f"(d[48]), "+f"(d[49]), "+f"(d[50]), "+f"(d[51]), "+f"(d[52]), "+f"(d[53]), "+f"(d[54]), "+f"(d[55]), "+f"(d[56]), "+f"(d[57]), "+f"(d[58]), "+f"(d[59]), "+f"(d[60]), "+f"(d[61]), "+f"(d[62]), "+f"(d[63])
        : "r"(a.x), "r"(a.y), "r"(a.z), "r"(a.w), "r"(descB), "r"(scaleD));
}

struct Ctx {
    uint32_t sb;
    uint32_t layer;
    int rw, sl, tid;
    __device__ __forceinline__ uint32_t bfull() const { return sb + SM_BAR; }
    __device__ __forceinline__ uint32_t bempty() const { return sb + SM_BAR + 64; }
    __device__ __forceinline__ uint32_t aempty() const { return sb + SM_BAR + 128 + (rw & 1) * 32; }
    __device__ __forceinline__ uint32_t afull() const { return sb + SM_BAR + 192 + (rw & 1) * 32; }
    __device__ __forceinline__ uint32_t done() const { return sb + SM_BAR + 256; }
    __device__ __forceinline__ uint32_t zbar() const { return sb + SM_BAR + 264; }
    __device__ __forceinline__ uint32_t aslot(uint32_t i) const { return sb + SM_A + ((rw & 1) * 4 + i) * 16384; }
    __device__ __forceinline__ int wg() const { return rw & 1; }
    __device__ __forceinline__ int warp() const { return tid >> 5; }
    __device__ __forceinline__ int lane() const { return tid & 31; }
    __device__ __forceinline__ void fresh() { asm volatile("" : "+r"(sb), "+r"(rw), "+r"(sl), "+r"(tid), "+r"(layer)); }
};

__device__ __forceinline__ uint32_t b_bar(const Ctx& c, int i) { return c.bfull() + (i % RING) * 8; }
__device__ __forceinline__ uint32_t b_par(int i) { return (i / RING) & 1; }
__device__ __forceinline__ uint32_t b_desc(const Ctx& c, int i) { return mkdesc(c.sb) + (i % RING) * 1024; }
__device__ __forceinline__ uint32_t a_par(const Ctx& c, int use, int slot) { return (use & 1) ^ (slot < 3 ? c.layer : 0u); }
__device__ __forceinline__ void b_release(const Ctx& c, int i) { if (c.lane() == 0) mbar_arrive(c.bempty() + (i % RING) * 8); }
__device__ __forceinline__ void a_release(const Ctx& c, int slot) { if (c.lane() == 0) mbar_arrive(c.aempty() + slot * 8); }
__device__ __forceinline__ void tt(const Ctx&) {}

__device__ __forceinline__ uint32_t tile_addr(uint32_t tile, int warp, int lane, int j) {
    int row = warp * 16 + (lane & 7) + ((lane >> 3) & 1) * 8;
    int chunk = 2 * j + (lane >> 4);
    return tile + row * 128 + ((chunk ^ (row & 7)) << 4);
}

__device__ __forceinline__ const uint4* stats_src(const Ctx& c) { return g_st + c.rw * 256 + 2 * (c.lane() & 3) * 32 + c.warp() * 8 + (c.lane() >> 2); }
template <uint32_t TAG>
__device__ __forceinline__ void get_stats(const Ctx& c, uint4 (&s)[2], float& m0, float& m1, float& r0, float& r1) {
    while (__builtin_expect(((s[0].x ^ TAG) | (s[1].x ^ TAG)) & 1u, 0)) { s[0] = ld_strong(stats_src(c)); s[1] = ld_strong(stats_src(c) + 32); }
    __syncwarp();
    float a0 = __uint_as_float(s[0].x), a1 = __uint_as_float(s[1].x), b0 = __uint_as_float(s[0].z), b1 = __uint_as_float(s[1].z);
    float ma = a0 + a1, mb = b0 + b1;
    ma += __shfl_xor_sync(0xffffffffu, ma, 1); mb += __shfl_xor_sync(0xffffffffu, mb, 1);
    ma += __shfl_xor_sync(0xffffffffu, ma, 2); mb += __shfl_xor_sync(0xffffffffu, mb, 2);
    ma *= 0.125f; mb *= 0.125f;
    float va = __uint_as_float(s[0].y) + __uint_as_float(s[1].y) + 64.f * ((a0 - ma) * (a0 - ma) + (a1 - ma) * (a1 - ma));
    float vb = __uint_as_float(s[0].w) + __uint_as_float(s[1].w) + 64.f * ((b0 - mb) * (b0 - mb) + (b1 - mb) * (b1 - mb));
    va += __shfl_xor_sync(0xffffffffu, va, 1); vb += __shfl_xor_sync(0xffffffffu, vb, 1);
    va += __shfl_xor_sync(0xffffffffu, va, 2); vb += __shfl_xor_sync(0xffffffffu, vb, 2);
    r0 = rsqrtf(va * (1.f / 512.f) + 1e-5f); r1 = rsqrtf(vb * (1.f / 512.f) + 1e-5f);
    m0 = ma; m1 = mb;
}

__device__ __forceinline__ void put_hint(const Ctx& c, uint32_t* hints, uint32_t tag) {
    __syncwarp();
    if (c.lane() == 0) asm volatile("st.relaxed.gpu.global.u32 [%0], %1;" :: "l"(hints + c.sl * 4 + c.warp()), "r"(tag) : "memory");
}
struct Tagger {
    uint32_t mask[4], bits;
    __device__ __forceinline__ Tagger(const Ctx& c, uint32_t tag) {
        bits = 0u - tag;
#pragma unroll
        for (int m = 0; m < 4; m++) mask[m] = 1u >> (c.lane() ^ m);
    }
    __device__ __forceinline__ uint32_t operator()(uint32_t v, int m) const {
        uint32_t r; asm("lop3.b32 %0, %1, %2, %3, 0xB8;" : "=r"(r) : "r"(v), "r"(mask[m]), "r"(bits)); return r;
    }
};
template <int N> __device__ __forceinline__ void pin(float (&d)[N]) {
#pragma unroll
    for (int i = 0; i < N; i++) asm volatile("" : "+f"(d[i]));
}
__device__ __forceinline__ void take_turns(const Ctx& c, uint32_t step) { const uint32_t d = (c.sl >> 1) * step + c.wg() * W1_DELAY; if (d) spin(d); }
__device__ __forceinline__ void put_lines(const Ctx& c, uint4* chunk, const uint4 (&x)[4], uint32_t tag) {
    uint32_t* dst = reinterpret_cast<uint32_t*>(chunk) + c.warp() * 64 + c.lane();
    const Tagger t(c, tag);
#pragma unroll
    for (int j = 0; j < 4; j++) { dst[j * 512] = t(x[j].x, 0); dst[j * 512 + 32] = t(x[j].y, 1); dst[j * 512 + 256] = t(x[j].z, 2); dst[j * 512 + 288] = t(x[j].w, 3); }
}
template <uint32_t TAG>
__device__ __forceinline__ void publish_x(const Ctx& c, const uint4 (&x)[4]) {
    put_lines(c, g_xa + (c.rw * 8 + c.sl) * 512, x, TAG);
    put_hint(c, g_xh + c.rw * 32, TAG);
    float sa[2] = {0.f, 0.f}, sb[2] = {0.f, 0.f}, qa[2] = {0.f, 0.f}, qb[2] = {0.f, 0.f};
#pragma unroll
    for (int j = 0; j < 4; j++) {
        const uint32_t wa[2] = {x[j].x, x[j].z}, wb[2] = {x[j].y, x[j].w};
#pragma unroll
        for (int h = 0; h < 2; h++) {
            const float a0 = __uint_as_float(wa[h] << 16), a1 = __uint_as_float(wa[h] & 0xffff0000u);
            const float b0 = __uint_as_float(wb[h] << 16), b1 = __uint_as_float(wb[h] & 0xffff0000u);
            sa[h] += a0 + a1; qa[h] = fmaf(a0, a0, fmaf(a1, a1, qa[h]));
            sb[h] += b0 + b1; qb[h] = fmaf(b0, b0, fmaf(b1, b1, qb[h]));
        }
    }
    const bool hi = c.lane() & 2;
    float s = sa[0] + sa[1], q = qa[0] + qa[1], s2 = sb[0] + sb[1], q2 = qb[0] + qb[1];
    float s0 = (hi ? s2 : s) + __shfl_xor_sync(0xffffffffu, hi ? s : s2, 2), q0 = (hi ? q2 : q) + __shfl_xor_sync(0xffffffffu, hi ? q : q2, 2);
    s0 += __shfl_xor_sync(0xffffffffu, s0, 1); q0 += __shfl_xor_sync(0xffffffffu, q0, 1);
    const float m = s0 * (1.f / 64.f), v = fmaxf(q0 - s0 * m, 0.f);
    const float m2 = __shfl_xor_sync(0xffffffffu, m, 2), v2 = __shfl_xor_sync(0xffffffffu, v, 2);
    if ((c.lane() & 3) == 0)
        st_strong(g_st + (c.rw * 8 + c.sl) * 32 + c.warp() * 8 + (c.lane() >> 2), make_uint4((__float_as_uint(m) & ~1u) | TAG, __float_as_uint(v), __float_as_uint(m2), __float_as_uint(v2)));
}

template <int ND>
__device__ __forceinline__ void seed_x(const uint4 (&x)[4], float (&d)[ND]) {
#pragma unroll
    for (int j = 0; j < 4; j++) {
        const uint32_t w[4] = {x[j].x, x[j].y, x[j].z, x[j].w};
#pragma unroll
        for (int m = 0; m < 4; m++) { d[8 * j + 2 * m] = __uint_as_float(w[m] << 16); d[8 * j + 2 * m + 1] = __uint_as_float(w[m] & 0xffff0000u); }
    }
}
template <int ND>
__device__ __forceinline__ void pack_x(const float (&d)[ND], uint4 (&x)[4]) {
#pragma unroll
    for (int j = 0; j < 4; j++)
        x[j] = make_uint4(pack_bf16(d[8 * j], d[8 * j + 1]), pack_bf16(d[8 * j + 2], d[8 * j + 3]), pack_bf16(d[8 * j + 4], d[8 * j + 5]), pack_bf16(d[8 * j + 6], d[8 * j + 7]));
}
__device__ __forceinline__ uint32_t tile_peek(const Ctx& c, uint32_t phys, bool on, uint32_t tag) {
    uint32_t v = tag;
    if (on)
        asm volatile("ld.shared.b32 %0, [%1];" : "=r"(v) : "r"(c.aslot(phys) + (c.lane() >> 1) * 1024 + (2 * c.warp() + (c.lane() & 1)) * 128 + (c.lane() & 3) * 4) : "memory");
    return v;
}
__device__ __noinline__ void tile_fix(uint32_t tile, const uint4* gtile, uint32_t b0, uint32_t b1, uint32_t cfg, float4* buf, uint32_t used, uint32_t bad) {
    const uint32_t lane = threadIdx.x & 31, off = ((threadIdx.x >> 5) & 3) * 256 + lane * 4, spb = (cfg >> 4) & 15, tag = cfg >> 13;
    if (!used) {
#pragma unroll 1
        for (int j = 0; j < 16; j++) buf[j * 128] = make_float4(0.f, 0.f, 0.f, 0.f);
    }
#pragma unroll 1
    for (uint32_t k = 0; k < 8; k++) {
        if (((bad >> (4 * k)) & 15) == 0) continue;
        uint32_t o[4], n[4];
#pragma unroll
        for (int m = 0; m < 4; m++) {
            const uint32_t p = k * 2048 + (m >> 1) * 1024 + (m & 1) * 128 + off;
            asm volatile("ld.shared.b32 %0, [%1];" : "=r"(o[m]) : "r"(tile + p) : "memory");
            do { n[m] = ld_strong32(reinterpret_cast<const char*>(gtile) + p); } while ((__shfl_sync(0xffffffffu, n[m], m) ^ tag) & 1u);
            if (cfg & 4096) asm volatile("st.shared.b32 [%0], %1;" :: "r"(tile + p), "r"(n[m]) : "memory");
            o[m] ^= 0x80008000u;
        }
        const uint32_t q = (cfg >> 16) + k, row = lane & 15;
        const uint32_t b = spb == 0 ? b0 + (36 + q / 6) % RING * 16384 + (q / 3 & 1) * 8192 + q % 3 * 2048 : k < spb ? b0 + k * 2048 : b1 + (k - spb) * 2048;
#pragma unroll 1
        for (uint32_t j = 0; j < ((cfg >> 6) & 12); j++) {
            const uint4 f = ldsm4t(b + (j >> 2) * 8192 + row * 128 + (((2 * (j & 3) + (lane >> 4)) ^ (row & 7)) << 4));
            const float4 p = buf[j * 256], q = buf[j * 256 + 128];
            float f0[4] = {p.x, p.y, p.z, p.w}, f1[4] = {q.x, q.y, q.z, q.w};
            mma16816_acc(f0, make_uint4(n[0], n[1], n[2], n[3]), f.x, f.y); mma16816_acc(f0, make_uint4(o[0], o[1], o[2], o[3]), f.x, f.y);
            mma16816_acc(f1, make_uint4(n[0], n[1], n[2], n[3]), f.z, f.w); mma16816_acc(f1, make_uint4(o[0], o[1], o[2], o[3]), f.z, f.w);
            buf[j * 256] = make_float4(f0[0], f0[1], f0[2], f0[3]); buf[j * 256 + 128] = make_float4(f1[0], f1[1], f1[2], f1[3]);
        }
    }
    asm volatile("fence.proxy.async.shared::cta;" ::: "memory");
    __syncwarp();
}
__device__ __forceinline__ uint32_t stale(uint32_t v, uint32_t tag) { return __ballot_sync(0xffffffffu, (v ^ tag) & 1u); }
template <int NF, bool PATCH, int SPB, int S0>
__device__ __forceinline__ void tile_settle(const Ctx& c, uint32_t bad, uint32_t tag, int slot, const uint4* gtile, uint32_t& fix) {
    if (__builtin_expect(bad != 0, 0)) {
        tile_fix(c.aslot(slot), gtile, c.sb + (SPB ? (S0 % RING) * 16384 : 0), c.sb + ((S0 + 1) % RING) * 16384,
                 SPB << 4 | (NF / 32) << 8 | PATCH << 12 | tag << 13 | (SPB ? 0 : S0) << 16, g_fix + (c.rw * 8 + c.sl) * 2048 + c.tid, fix, bad);
        fix = 1;
    }
}
template <int ND>
__device__ __forceinline__ void apply_fix(const Ctx& c, float (&d)[ND], uint32_t fix) {
    if (__builtin_expect(fix, 0)) {
        const float4* buf = g_fix + (c.rw * 8 + c.sl) * 2048 + c.tid;
#pragma unroll
        for (int j = 0; j < ND / 4; j++) { const float4 p = buf[j * 128]; d[4 * j] += p.x; d[4 * j + 1] += p.y; d[4 * j + 2] += p.z; d[4 * j + 3] += p.w; }
    }
}
struct ADesc {
    uint32_t hi, step;
    __device__ __forceinline__ ADesc(const Ctx& c, bool raw) { const bool r = raw && c.layer == 0; hi = r ? 0x40000040u : 8u; step = r ? 2u : 128u; }
    __device__ __forceinline__ uint32_t at(uint32_t base, int j) const { return base + (j >> 2) * 512 + (j & 3) * step; }
};
template <int I0, bool OWN, int T = 0, class W, int ND, class F>
__device__ __forceinline__ void narrow_pass(const Ctx& c, float (&d)[ND], W mma, uint32_t& fix, F last, uint32_t vp = 0) {
    if (OWN) mbar_wait2(c.afull() + T * 8, a_par(c, 1, T), b_bar(c, I0 + T), b_par(I0 + T)); else mbar_wait(b_bar(c, I0 + T), b_par(I0 + T));
    if (T == 0) tt(c);
    const ADesc da(c, I0 == 8);
    uint32_t v = 0;
    if (OWN) v = tile_peek(c, T, 2 * T + (c.lane() >> 4) != c.sl, 1);
#pragma unroll
    for (int g = 0; g < 2; g++) {
        if (!OWN || 2 * T + g != c.sl) {
            wg_fence();
#pragma unroll
            for (int j = 4 * g; j < 4 * g + 4; j++) mma(d, da.at(mkdesc_a(c.aslot(T)), j), da.hi, b_desc(c, I0 + T) + j * 128, (T | j) != 0 || OWN);
        }
    }
    wg_commit();
    if constexpr (T > 0) {
        wg_wait<1>();
        if (OWN) tile_settle<32, false, 8, I0 + T - 1>(c, stale(vp, 1), 1, T - 1, g_oa + c.rw * 4096 + (T - 1) * 1024, fix);
        a_release(c, T - 1); b_release(c, I0 + T - 1);
    }
    if constexpr (T < 3) narrow_pass<I0, OWN, T + 1>(c, d, mma, fix, last, v);
    else {
        last();
        wg_wait<0>();
        if (OWN) tile_settle<32, false, 8, I0 + T>(c, stale(v, 1), 1, T, g_oa + c.rw * 4096 + T * 1024, fix);
        a_release(c, T); b_release(c, I0 + T);
        tt(c);
    }
}
template <int I0, uint32_t TAG>
__device__ __forceinline__ void x_pass(const Ctx& c, float (&d)[64], uint32_t& fix, const uint4 (&x)[4], float& m0, float& m1, float& r0, float& r1) {
    const ADesc da(c, I0 == 0);
    const bool check = !(I0 == 0 && c.layer == 0);
    const uint32_t a0 = mkdesc_a(c.aslot(0)), peek = c.aslot(0) + ((c.lane() & 15) >> 1) * 1024 + (2 * c.warp() + (c.lane() & 1)) * 128 + (c.lane() & 3) * 4;
    mbar_wait(b_bar(c, I0), b_par(I0));
    tt(c);
    wg_fence();
#pragma unroll
    for (int j = 0; j < 4; j++) wgmma_rs_n128(d, x[j], b_desc(c, I0) + j * 128, j != 0);
    wg_commit();
    wg_wait<0>(); b_release(c, I0);
    uint32_t vp = TAG, kp = 0, st = I0 % RING, bp = b_par(I0);
    mbar_wait(c.afull(), c.layer);
    uint4 s[2] = {ld_strong(stats_src(c)), ld_strong(stats_src(c) + 32)};
    auto settle = [&](uint32_t groups) {
        const uint32_t bad = stale(vp, TAG);
        if (__builtin_expect(bad != 0, 0)) {
            tile_fix(c.aslot(0) + kp * 8192, g_xa + c.rw * 4096 + kp * 512, c.sb + st * 16384, 0, 4 << 4 | groups << 8 | 1 << 12 | TAG << 13,
                     g_fix + (c.rw * 8 + c.sl) * 2048 + c.tid, groups ? fix : 1u, bad);
            if (groups) fix = 1;
        }
    };
    auto look = [&](uint32_t kc) {
        uint32_t v = TAG;
        if (check && c.lane() < 16) asm volatile("ld.shared.b32 %0, [%1];" : "=r"(v) : "r"(peek + kc * 8192) : "memory");
        return v;
    };
#pragma unroll 1
    for (uint32_t h = 0; h < 7; h++) {
        const uint32_t kc = h + (h >= (uint32_t)c.sl), ns = st == RING - 1 ? 0 : st + 1;
        bp ^= ns == 0;
        mbar_wait2(c.afull() + (kc >> 1) * 8, kc < 6 ? c.layer : 0u, c.bfull() + ns * 8, bp);
        const uint32_t v = look(kc);
        wg_fence();
#pragma unroll
        for (int j = 0; j < 4; j++) wgmma_n128(d, da.at(a0 + kc * 512, j), da.hi, mkdesc(c.sb) + ns * 1024 + j * 128, 1);
        wg_commit();
        wg_wait<1>();
        settle(2);
        if (h && c.lane() == 0) mbar_arrive(c.bempty() + st * 8);
        vp = v; kp = kc; st = ns;
    }
    const uint32_t v = look(c.sl);
    get_stats<TAG>(c, s, m0, m1, r0, r1);
    wg_wait<0>();
#pragma unroll 1
    for (int e = 2; e >= 0; e -= 2) {
        settle(e);
        if (e && c.lane() == 0) mbar_arrive(c.bempty() + st * 8);
        vp = v; kp = c.sl;
    }
    tt(c);
}
template <int T = 0>
__device__ __forceinline__ void h_pass(const Ctx& c, float (&d)[64], uint32_t& fix, const uint4* g, uint32_t tag, uint32_t badp = 0) {
    constexpr int S = 28 + 2 * T;
    mbar_wait2(c.afull() + T * 8, a_par(c, 1, T), b_bar(c, S), b_par(S));
    if (T == 0) tt(c);
    const uint32_t v = tile_peek(c, T, true, tag);
    wg_fence();
#pragma unroll
    for (int j = 0; j < 4; j++) wgmma_n128(d, mkdesc_a(c.aslot(T)) + j * 128, 8u, b_desc(c, S) + j * 128, 1);
    wg_commit();
    if constexpr (T > 0) {
        wg_wait<1>();
        tile_settle<64, false, 4, S - 2>(c, badp, tag, T - 1, g + (T - 1) * 1024, fix);
        a_release(c, T - 1);
        if (badp) b_release(c, S - 2);
        b_release(c, S - 1);
    }
    mbar_wait(b_bar(c, S + 1), b_par(S + 1));
    wg_fence();
#pragma unroll
    for (int j = 0; j < 4; j++) wgmma_n128(d, mkdesc_a(c.aslot(T)) + (4 + j) * 128, 8u, b_desc(c, S + 1) + j * 128, 1);
    wg_commit();
    const uint32_t bad = stale(v, tag);
    wg_wait<1>();
    if (!bad) b_release(c, S);
    if constexpr (T < 3) h_pass<T + 1>(c, d, fix, g, tag, bad);
    else {
        wg_wait<0>();
        tile_settle<64, false, 4, S>(c, bad, tag, T, g + T * 1024, fix);
        a_release(c, T);
        if (bad) b_release(c, S);
        b_release(c, S + 1);
        tt(c);
    }
}
template <bool WIDE, int ND>
__device__ __forceinline__ void fold_mean(const Ctx& c, float (&d)[ND], uint32_t cs, float m0, float m1) {
    if (c.layer == 0) mbar_wait(c.zbar() + (cs == SM_ONES || cs == SM_CS ? 24 : 32), 0);
    cs += c.sb + (c.lane() & 3) * 8;
#pragma unroll
    for (int b = 0; b < ND / 4; b++) {
        float c0, c1;
        asm volatile("ld.shared.v2.f32 {%0, %1}, [%2];" : "=f"(c0), "=f"(c1) : "r"(cs + (WIDE ? (b >> 1) * 128 + ((b & 8) ? 0 : 64) + (b & 1) * 32 : b * 32)) : "memory");
        d[4 * b] = fmaf(-m0, c0, d[4 * b]); d[4 * b + 1] = fmaf(-m0, c1, d[4 * b + 1]); d[4 * b + 2] = fmaf(-m1, c0, d[4 * b + 2]); d[4 * b + 3] = fmaf(-m1, c1, d[4 * b + 3]);
    }
}
template <int T>
__device__ __forceinline__ uint32_t h48_tile(const Ctx& c, float (&d)[32], uint32_t tag) {
    mbar_wait2(c.afull() + T * 8, a_par(c, 0, T), b_bar(c, 37 + T), b_par(37 + T));
    const uint32_t v = tile_peek(c, T, true, tag);
    wg_fence();
#pragma unroll
    for (int j = 0; j < (T < 2 ? 8 : 6); j++) {
        const int q = 8 * T + j;
        wgmma_n64(d, mkdesc_a(c.aslot(T)) + j * 128, 8u, b_desc(c, 36 + q / 6) + (q / 3 & 1) * 512 + q % 3 * 128, 1);
    }
    wg_commit();
    return v;
}
__device__ __forceinline__ void ffn2(const Ctx& c, uint4 (&xn)[4]) {
    float dd[64]; uint32_t fix = 0;
    seed_x(xn, dd);
#pragma unroll
    for (int i = 32; i < 64; i++) dd[i] = 0.f;
    pin(dd);
    const uint32_t tag = c.layer ^ 1;
    h_pass(c, dd, fix, g_h + (c.rw * 88 + 32 * (c.sl & 1)) * 128, tag);
    apply_fix(c, dd, fix);
    uint4 r[4];
#pragma unroll
    for (int j = 0; j < 4; j++) {
        const float* p = dd + 32 + 8 * j;
        r[j] = make_uint4(pack_bf16(p[0], p[1]), pack_bf16(p[2], p[3]), pack_bf16(p[4], p[5]), pack_bf16(p[6], p[7]));
    }
    put_lines(c, g_oa + (c.rw * 8 + (c.sl ^ 1)) * 512, r, 0);
    float (&d)[32] = *reinterpret_cast<float (*)[32]>(dd);
    const uint4* g = g_h + (c.rw * 88 + 64) * 128;
    fix = 0;
    mbar_wait(b_bar(c, 36), b_par(36));
    tt(c);
    const uint32_t v0 = h48_tile<0>(c, d, tag), v1 = h48_tile<1>(c, d, tag);
    wg_wait<1>(); tile_settle<32, false, 0, 0>(c, stale(v0, tag), tag, 0, g, fix); a_release(c, 0); b_release(c, 36);
    const uint32_t v2 = h48_tile<2>(c, d, tag);
    const uint32_t* src = reinterpret_cast<const uint32_t*>(g_oa + (c.rw * 8 + c.sl) * 512) + c.warp() * 64 + c.lane();
    uint32_t u[16];
#pragma unroll
    for (int i = 0; i < 16; i++) u[i] = ld_strong32(src + (i >> 2) * 512 + ((i >> 1) & 1) * 256 + (i & 1) * 32);
    wg_wait<1>(); tile_settle<32, false, 0, 8>(c, stale(v1, tag), tag, 1, g + 1024, fix); a_release(c, 1); b_release(c, 37);
    wg_wait<0>(); tile_settle<32, false, 0, 16>(c, stale(v2, tag), tag, 2, g + 2048, fix); a_release(c, 2); b_release(c, 38); b_release(c, 39);
    tt(c);
    TS(15 + c.layer * 16);
    apply_fix(c, d, fix);
    while (true) {
        const uint32_t b0 = u[0] | u[4] | u[8] | u[12], b1 = u[1] | u[5] | u[9] | u[13], b2 = u[2] | u[6] | u[10] | u[14], b3 = u[3] | u[7] | u[11] | u[15];
        const int l = c.lane();
        if (!__any_sync(0xffffffffu, (l == 0 ? b0 : l == 1 ? b1 : l == 2 ? b2 : l == 3 ? b3 : 0u) & 1u)) break;
#pragma unroll
        for (int i = 0; i < 16; i++) u[i] = ld_strong32(src + (i >> 2) * 512 + ((i >> 1) & 1) * 256 + (i & 1) * 32);
    }
#pragma unroll
    for (int i = 0; i < 16; i++) { d[2 * i] += __uint_as_float(u[i] << 16); d[2 * i + 1] += __uint_as_float(u[i] & 0xffff0000u); }
    pack_x(d, xn);
}
__device__ __forceinline__ uint32_t pack_relu(float lo, float hi) { uint32_t r; asm("cvt.rn.relu.bf16x2.f32 %0, %1, %2;" : "=r"(r) : "f"(hi), "f"(lo)); return r; }
template <int PART, int NA>
__device__ __forceinline__ void publish_h(const Ctx& c, const float (&d)[NA], float r0, float r1) {
    uint32_t* dst = reinterpret_cast<uint32_t*>(g_h + (c.rw * 88 + (PART ? 64 + 3 * c.sl : 8 * c.sl)) * 128) + c.warp() * 64 + c.lane();
    const uint32_t tag = c.layer ^ 1;
    const Tagger t(c, tag);
#pragma unroll
    for (int j = 0; j < NA / 4; j++) {
        dst[j * 256] = t(pack_relu(d[4 * j] * r0, d[4 * j + 1] * r0), 2 * j & 3);
        dst[j * 256 + 32] = t(pack_relu(d[4 * j + 2] * r1, d[4 * j + 3] * r1), (2 * j + 1) & 3);
    }
    put_hint(c, g_hf + (c.rw * 2 + PART) * 32, tag);
}

__device__ __forceinline__ void colsum_load(const Ctx& c, int g, const char* wq, const char* w1, uint4 (&v)[8]) {
    const int lane = threadIdx.x & 31, col = g < 3 ? (g + 1) % 3 * 512 + 64 * c.sl + (lane & 7) * 8 : 176 * c.sl + 64 * (g - 3) + (lane & 7) * 8;
    const uint32_t pitch = g < 3 ? 3072 : 2752;
    const char* q = (g < 3 ? wq + col * 2 : w1 + min(col, 1368) * 2) + ((c.rw >> 1) * 32 + (lane >> 3) * 8) * pitch;
    asm volatile("ld.global.nc.v4.u32 {%0,%1,%2,%3}, [%16];\n ld.global.nc.v4.u32 {%4,%5,%6,%7}, [%17];\n ld.global.nc.v4.u32 {%8,%9,%10,%11}, [%18];\n ld.global.nc.v4.u32 {%12,%13,%14,%15}, [%19];"
                 : "=r"(v[0].x), "=r"(v[0].y), "=r"(v[0].z), "=r"(v[0].w), "=r"(v[1].x), "=r"(v[1].y), "=r"(v[1].z), "=r"(v[1].w),
                   "=r"(v[2].x), "=r"(v[2].y), "=r"(v[2].z), "=r"(v[2].w), "=r"(v[3].x), "=r"(v[3].y), "=r"(v[3].z), "=r"(v[3].w)
                 : "l"(q), "l"(q + pitch), "l"(q + 2 * pitch), "l"(q + 3 * pitch));
    asm volatile("ld.global.nc.v4.u32 {%0,%1,%2,%3}, [%16];\n ld.global.nc.v4.u32 {%4,%5,%6,%7}, [%17];\n ld.global.nc.v4.u32 {%8,%9,%10,%11}, [%18];\n ld.global.nc.v4.u32 {%12,%13,%14,%15}, [%19];"
                 : "=r"(v[4].x), "=r"(v[4].y), "=r"(v[4].z), "=r"(v[4].w), "=r"(v[5].x), "=r"(v[5].y), "=r"(v[5].z), "=r"(v[5].w),
                   "=r"(v[6].x), "=r"(v[6].y), "=r"(v[6].z), "=r"(v[6].w), "=r"(v[7].x), "=r"(v[7].y), "=r"(v[7].z), "=r"(v[7].w)
                 : "l"(q + 4 * pitch), "l"(q + 5 * pitch), "l"(q + 6 * pitch), "l"(q + 7 * pitch));
}
__device__ __forceinline__ void colsum_add(const Ctx& c, int g, const uint4 (&v)[8]) {
    const int lane = threadIdx.x & 31;
    float s[8] = {};
#pragma unroll
    for (int i = 0; i < 8; i++) {
        const uint32_t w[4] = {v[i].x, v[i].y, v[i].z, v[i].w};
#pragma unroll
        for (int m = 0; m < 4; m++) { s[2 * m] += __uint_as_float(w[m] << 16); s[2 * m + 1] += __uint_as_float(w[m] & 0xffff0000u); }
    }
#pragma unroll
    for (int m = 0; m < 8; m++) {
        s[m] += __shfl_xor_sync(0xffffffffu, s[m], 8); s[m] += __shfl_xor_sync(0xffffffffu, s[m], 16);
        if (g >= 3 && 176 * c.sl + 64 * (g - 3) + (lane & 7) * 8 >= 1376) s[m] = 0.f;
    }
    const int u = lane >> 3;
    if (u < 3) red_add4(g_cs + c.sl * 144 + 8 * g + (lane & 7) + 48 * u, u == 0 ? s[0] : u == 1 ? s[3] : s[6], u == 0 ? s[1] : u == 1 ? s[4] : s[7], u == 0 ? s[2] : s[5], 1.f);
}

__device__ __forceinline__ int role_of(uint32_t smid, uint32_t nsm) {
    if (nsm != 132) return blockIdx.x;
    int tpc = smid >> 1, lo = smid & 1, grp, idx;
    if (smid >= 124) { grp = 7; idx = 4 + (tpc - 62); }
    else if (smid >= 120) return 128;
    else if (smid < 64) { int g = tpc & 7; idx = tpc >> 3; grp = g == 0 ? 7 : g - 1; }
    else { grp = (tpc - 32) % 7; idx = 4 + (tpc - 32) / 7; }
    return (grp * 2 + lo) * 8 + idx;
}

__global__ void __launch_bounds__(384, 1)
fused_kernel(const __grid_constant__ CUtensorMap tm_x, const __grid_constant__ CUtensorMap tm_qkv, const __grid_constant__ CUtensorMap tm_wo, const __grid_constant__ CUtensorMap tm_w1,
             const __grid_constant__ CUtensorMap tm_w2, const __grid_constant__ CUtensorMap tm_w2b,
             const __nv_bfloat16* __restrict__ x_in, const char* __restrict__ wq_p, const char* __restrict__ wo_p, const char* __restrict__ w1_p, const char* __restrict__ w2_p,
             __nv_bfloat16* __restrict__ out, int nsm) {
    extern __shared__ __align__(1024) char smem_raw[];
    uint32_t smid; asm volatile("mov.u32 %0, %%smid;" : "=r"(smid));
    const int role = role_of(smid, nsm);
    if (role >= 128) return;
    Ctx c;
    c.sb = (uint32_t)__cvta_generic_to_shared(smem_raw);
    asm volatile("mov.u32 %0, %0;" : "+r"(c.sb));
    const int warp_id = __shfl_sync(0xffffffffu, threadIdx.x >> 5, 0);
    c.rw = (role >> 3) * 2 + ((warp_id >> 2) & 1); c.sl = role & 7; c.tid = threadIdx.x & 127;
    c.layer = 0;
    TS(0);
    if (threadIdx.x == 288) { asm volatile("prefetch.tensormap [%0];" :: "l"(&tm_wo) : "memory"); asm volatile("prefetch.tensormap [%0];" :: "l"(&tm_w1) : "memory");
                              asm volatile("prefetch.tensormap [%0];" :: "l"(&tm_w2) : "memory"); asm volatile("prefetch.tensormap [%0];" :: "l"(&tm_w2b) : "memory"); }
    uint4 x0[4];
    if (warp_id < 8) {
        const __nv_bfloat16* p = x_in + (size_t)(c.rw * 64 + c.warp() * 16 + (c.lane() >> 3)) * 512 + c.sl * 64 + (c.lane() & 7) * 8;
#pragma unroll
        for (int i = 0; i < 4; i++) x0[i] = __ldg(reinterpret_cast<const uint4*>(p + i * 4 * 512));
    }
    TSG(62);
    if (warp_id >= 8 && elect_one()) {
        const uint32_t cnt = warp_id == 9 ? 8 : warp_id == 10 ? 4 : 1;
#pragma unroll
        for (int i = 0; i < 8; i++) mbar_init(c.bfull() + (warp_id - 8) * 64 + i * 8, cnt);
        mbar_init(c.done() + (warp_id - 8) * 16, warp_id == 8 ? 8 : warp_id == 11 ? 4 : 1); mbar_init(c.done() + (warp_id - 8) * 16 + 8, warp_id == 8 ? 8 : 1);
        asm volatile("fence.mbarrier_init.release.cluster;" ::: "memory");
        if (warp_id == 11) {
#pragma unroll
            for (int i = 0; i < 4; i++) {
                const uint32_t bar = c.afull() + (i & 1) * 32 + (i >> 1) * 8, dst = c.aslot(0) + (i & 1) * 65536 + (i >> 1) * 16384;
                mbar_expect_tx(bar, 16384);
                tma2d(dst, &tm_x, (i >> 1) * 128, (c.rw + (i & 1)) * 64, bar); tma2d(dst + 8192, &tm_x, (i >> 1) * 128 + 64, (c.rw + (i & 1)) * 64, bar);
            }
        }
        if (warp_id == 8) {
#pragma unroll
            for (int i = 0; i < 3; i++) {
                mbar_expect_tx(c.bfull() + i * 8, 16384);
                const int row = (i == 0 ? c.sl : i - 1 + (i - 1 >= c.sl)) * 64;
                tma2d(c.sb + i * 16384, &tm_qkv, 512 + 64 * c.sl, row, c.bfull() + i * 8); tma2d(c.sb + i * 16384 + 8192, &tm_qkv, 1024 + 64 * c.sl, row, c.bfull() + i * 8);
            }
        }
    }
    __syncthreads();

    TS(44);
    if (warp_id >= 8) {
        asm volatile("setmaxnreg.dec.sync.aligned.u32 56;");
        if (warp_id == 8) {
            uint32_t slot = 3, ph = 1;
            for (int layer = 0; layer < 2; layer++) {
                for (int i = layer ? 0 : 3; i < 40; i++) {
                    const CUtensorMap* m; int col = 64 * c.sl, row = (i & 3) * 128, dcol = 0, drow = 64; uint32_t bytes = 16384;
                    const int h = i & 7, kc = h == 0 ? c.sl : h - 1 + (h - 1 >= c.sl);
                    if (i < 8) { m = &tm_qkv; col += 512; row = kc * 64; dcol = 512; drow = 0; }
                    else if (i < 12) { m = &tm_qkv; }
                    else if (i < 16) { m = &tm_wo; }
                    else if (i < 24) { m = &tm_w1; col = 176 * c.sl; row = kc * 64; dcol = 64; drow = 0; }
                    else if (i < 28) { m = &tm_w1; col = 176 * c.sl + 128; }
                    else if (i < 36) { m = &tm_w2; row = 176 * (4 * (c.sl & 1) + ((i - 28) >> 1)) + (i & 1) * 64; dcol = (c.sl & 1) ? -64 : 64; drow = 0; }
                    else { m = &tm_w2b; row = 352 * (i & 3) + 128; drow = 176; bytes = 12288; }
                    mbar_wait_bounded(c.bempty() + slot * 8, ph);
                    if (elect_one()) {
                        mbar_expect_tx(c.bfull() + slot * 8, bytes);
                        tma2d(c.sb + slot * 16384, m, col, row, c.bfull() + slot * 8);
                        tma2d(c.sb + slot * 16384 + 8192, m, col + dcol, row + drow, c.bfull() + slot * 8);
                    }
                    __syncwarp();
                    if (++slot == RING) { slot = 0; ph ^= 1; }
                }
            }
        } else if (warp_id < 11) {
            c.rw += warp_id - 9;
            const int lane = threadIdx.x & 31;
            if (elect_one()) {
#pragma unroll
                for (int i = 2; i < 4; i++) {
                    mbar_expect_tx(c.afull() + i * 8, 16384);
                    tma2d(c.aslot(i), &tm_x, i * 128, c.rw * 64, c.afull() + i * 8); tma2d(c.aslot(i) + 8192, &tm_x, i * 128 + 64, c.rw * 64, c.afull() + i * 8);
                }
            }
            __syncwarp();
            { uint4 w0[8]; colsum_load(c, c.wg(), wq_p, w1_p, w0); colsum_add(c, c.wg(), w0); }
            uint32_t ph = 0;
            TSW(2 + c.wg(), 0);
#pragma unroll 1
            for (int st = 1; st < 10; st++) {
                const int layer = st >= 5, k = st - layer * 5;
                const uint32_t* hint = (k == 1 ? g_oh + c.rw * 32 : k < 3 ? g_xh + c.rw * 32 : g_hf + (c.rw * 2 + k - 3) * 32) + lane;
                const uint4* src = k == 1 ? g_oa + c.rw * 4096 : k < 3 ? g_xa + c.rw * 4096 : g_h + (c.rw * 88 + (k == 4 ? 64 : 32 * (c.sl & 1))) * 128;
                const uint32_t tag = k == 0 ? 1 : k == 2 ? 0 : layer ^ 1;
                uint32_t need = k < 3 ? 0xffu : k == 3 ? 0xfu << (16 * (c.sl & 1)) : 0xfffu, dst = c.aslot(0), bar = c.afull(), it = 0;
                int left = k == 4 ? 3 : 4;
                auto arm = [&]() {
                    const uint32_t i = (bar - c.afull()) >> 3;
                    mbar_wait_bounded(c.aempty() + i * 8, (ph >> i) & 1);
                    if (elect_one()) mbar_expect_tx(bar, 16384);
                };
                auto step = [&](uint32_t v) {
                    const uint32_t seen = __ballot_sync(0xffffffffu, ((v ^ tag) & 1u) == 0);
                    while (left && (seen & need) == need) {
                        if (elect_one()) bulk1d(dst, src, 16384, bar);
                        if (left == (k == 4 ? 3 : 4)) TSW(2 + c.wg(), 1 + st);
                        dst += 16384; src += 1024; bar += 8;
                        need = k < 3 ? need << 8 : k == 3 ? need << 4 : left == 3 ? 0xffff00u : 0xfff00000u;
                        if (--left) { arm(); spin(k == 1 ? O_STAGGER : k < 3 ? STAGGER : H_STAGGER); }
                    }
                };
                arm();
                uint32_t v0 = ld_strong32(hint), v1;
                spin(POLL_GAP);
                while (true) {
                    v1 = ld_strong32(hint);
                    step(v0);
                    if (!left) break;
                    v0 = ld_strong32(hint);
                    step(v1);
                    if (!left) break;
                    if (++it > SPIN_LIMIT) __trap();
                }
                __syncwarp();
                ph ^= k == 4 ? 7 : 15;
            }
        } else {
            { uint4 w0[8]; colsum_load(c, 2, wq_p, w1_p, w0); colsum_add(c, 2, w0); }
            if (c.rw == 0) {
                for (int u = c.tid & 31; u < 384; u += 32) g_kv[(8 + c.sl) * 384 + u] = make_float4(0.f, 0.f, 0.f, 0.f);
                __threadfence();
                __syncwarp();
                if (elect_one()) mbar_arrive(c.zbar() + 16);
            }

            const int lane = c.tid & 31;
#pragma unroll 1
            for (int p = 0; p < 2; p++) {
                if (p == 1) {
                    if (elect_one()) { l2_prefetch(wo_p + role * 4096, 4096); l2_prefetch(w2_p + role * 11008, 11008); }
                    __syncwarp();
#pragma unroll 1
                    for (int g = 3; g < 6; g++) { uint4 w0[8]; colsum_load(c, g, wq_p, w1_p, w0); colsum_add(c, g, w0); }
                }
                const int ch = 24 * p + min(lane, 23 - 2 * p);
                uint4 v[3]; uint32_t it = 0;
                do {
#pragma unroll
                    for (int i = 0; i < 3; i++) v[i] = ld_strong(g_cs + c.sl * 144 + ch + 48 * i);
                    if (++it > SPIN_LIMIT) __trap();
                } while (__any_sync(0xffffffffu, ((v[0].w ^ 0x41800000u) | (v[1].w ^ 0x41800000u) | (v[2].w ^ 0x41800000u)) != 0));
                const int b = ch < 16 ? ch : ch - 8;
                const uint32_t a = c.sb + ((ch >= 16 && ch < 24) ? SM_CS + (ch - 16) * 32 : ch >= 40 ? SM_CS + (ch - 32) * 32 : SM_ONES + (b >> 1) * 128 + ((b & 8) ? 0 : 64) + (b & 1) * 32);
                sts128(a, make_uint4(v[0].x, v[0].y, v[0].z, v[1].x)); sts128(a + 16, make_uint4(v[1].y, v[1].z, v[2].x, v[2].y));
                __syncwarp();
                TSW(3, 42 + p);
                if (elect_one()) mbar_arrive(c.zbar() + 24 + 8 * p);
            }
            if (c.rw == 0) {
                mbar_wait_bounded(c.zbar() + 8, 0);
                for (int u = c.tid & 31; u < 384; u += 32) g_kv[c.sl * 384 + u] = make_float4(0.f, 0.f, 0.f, 0.f);
                for (int u = c.tid & 31; u < 144; u += 32) g_cs[c.sl * 144 + u] = make_float4(0.f, 0.f, 0.f, 0.f);
            }
            mbar_wait_bounded(c.done(), 0);
        }
    } else {
        asm volatile("setmaxnreg.inc.sync.aligned.u32 224;");
        if (c.wg() == 1) {
            sts128(c.sb + SM_ONES + c.tid * 16, make_uint4(0x3F803F80u, 0x3F803F80u, 0x3F803F80u, 0x3F803F80u));
            asm volatile("fence.proxy.async.shared::cta;" ::: "memory");
        }
        TS(46);
        uint4 xn[4];
        {
            const uint32_t tile = c.sb + SM_STG + c.wg() * 8192, srow = tile + (c.warp() * 16 + (c.lane() >> 3)) * 128;
#pragma unroll
            for (int i = 0; i < 4; i++) sts128(srow + i * 512 + (((c.lane() & 7) ^ ((c.lane() >> 3) + 4 * (i & 1))) << 4), x0[i]);
            __syncwarp();
#pragma unroll
            for (int j = 0; j < 4; j++) xn[j] = ldsm4(tile_addr(tile, c.warp(), c.lane(), j));
            TS(45);
            publish_x<1>(c, xn);
            TS(47);
            bar_sync(8, 256);
        }
        TS(1);
        auto mma64 = [](float (&d)[32], uint32_t a, uint32_t h, uint32_t b, int sd) { wgmma_n64(d, a, h, b, sd); };
        auto mma48 = [](float (&d)[24], uint32_t a, uint32_t h, uint32_t b, int sd) { wgmma_n48(d, a, h, b, sd); };
#pragma unroll 1
        for (c.layer = 0; c.layer < 2; c.layer++) {
            uint4 o[4];
            {
                float m0, m1, r0, r1;
                c.fresh();
                float acc[64];
                {
                    uint32_t fix = 0;
                    x_pass<0, 1>(c, acc, fix, xn, m0, m1, r0, r1);
                    apply_fix(c, acc, fix);
                }
                fold_mean<true>(c, acc, SM_ONES, m0, m1);
                TS(3 + c.layer * 16);
                c.fresh();
                const float l0 = r0 * 1.4426950408889634f, l1 = r1 * 1.4426950408889634f;
                {
                    const uint32_t tile = c.sb + SM_STG + c.wg() * 8192;
#pragma unroll
                    for (int j = 0; j < 4; j++)
                        stsm4(tile_addr(tile, c.warp(), c.lane(), j),
                              make_uint4(pack_bf16(phi(acc[8 * j], r0, l0), phi(acc[8 * j + 1], r0, l0)), pack_bf16(phi(acc[8 * j + 2], r1, l1), phi(acc[8 * j + 3], r1, l1)),
                                         pack_bf16(phi(acc[8 * j + 4], r0, l0), phi(acc[8 * j + 5], r0, l0)), pack_bf16(phi(acc[8 * j + 6], r1, l1), phi(acc[8 * j + 7], r1, l1))));
                    uint4 vv[4], kt[4];
#pragma unroll
                    for (int j = 0; j < 4; j++)
                        vv[j] = make_uint4(pack_bf16(acc[32 + 8 * j] * r0, acc[33 + 8 * j] * r0), pack_bf16(acc[34 + 8 * j] * r1, acc[35 + 8 * j] * r1),
                                           pack_bf16(acc[36 + 8 * j] * r0, acc[37 + 8 * j] * r0), pack_bf16(acc[38 + 8 * j] * r1, acc[39 + 8 * j] * r1));
                    bar_sync(1 + c.wg(), 128);
#pragma unroll
                    for (int j = 0; j < 4; j++) {
                        const uint32_t row = 16 * j + (c.lane() & 7) + (c.lane() >> 4) * 8, chunk = 2 * c.warp() + ((c.lane() >> 3) & 1);
                        kt[j] = ldsm4t(tile + row * 128 + ((chunk ^ (row & 7)) << 4));
                    }
#pragma unroll
                    for (int j = 0; j < 4; j++) asm volatile("" :: "r"(kt[j].w) : "memory");
                    bar_sync(1 + c.wg(), 128);
#pragma unroll
                    for (int j = 0; j < 4; j++) stsm4(tile_addr(tile, c.warp(), c.lane(), j), vv[j]);
                    asm volatile("fence.proxy.async.shared::cta;" ::: "memory");
                    bar_sync(1 + c.wg(), 128);
                    float dk[36], kv[8];
                    const uint32_t lbo = (c.sb + SM_ONES - tile) >> 4;
                    wg_fence();
#pragma unroll
                    for (int j = 0; j < 4; j++)
                        wgmma_rs_n72(dk, kt[j], (((tile & 0x3FFFF) >> 4) + j * 128) | ((lbo - j * 128) << 16), j > 0);
                    wg_commit();
                    wg_wait<0>();
                    const int w = c.warp(), t = c.lane() & 3;
#pragma unroll
                    for (int i = 0; i < 8; i++) kv[i] = sel4(w, dk[i], dk[8 + i], dk[16 + i], dk[24 + i]);
                    const float zz = t == 0 ? dk[32] : t == 1 ? dk[34] : 0.f;
                    if (c.rw == 0) mbar_wait(c.zbar() + 16, 0);
                    float4* kvp = g_kv + ((c.layer * 8 + c.sl) * 3) * 128 + c.tid;
                    red_add4(kvp, kv[0], kv[1], kv[2], 1.f);
                    red_add4(kvp + 128, kv[3], kv[4], kv[5], 1.f);
                    red_add4(kvp + 256, kv[6], kv[7], zz, 1.f);
                }
                c.fresh();
                TS(4 + c.layer * 16);
                float q[32]; uint32_t nofix;
                const float4* kvq = g_kv + ((c.layer * 8 + c.sl) * 3) * 128 + c.tid;
                const uint32_t share = c.sb + SM_STG;
                uint4 u0, u1, u2;
                auto fetch = [&]() { u0 = ld_strong(kvq); u1 = ld_strong(kvq + 128); u2 = ld_strong(kvq + 256); };
                auto put = [&]() {
                    if (__any_sync(0xffffffffu, ((u0.w ^ 0x42000000u) | (u1.w ^ 0x42000000u) | (u2.w ^ 0x42000000u)) != 0)) return false;
                    stsm4(share + c.tid * 16, make_uint4(pack_bf16(__uint_as_float(u0.x), __uint_as_float(u0.y)), pack_bf16(__uint_as_float(u0.z), __uint_as_float(u1.x)),
                                                         pack_bf16(__uint_as_float(u1.y), __uint_as_float(u1.z)), pack_bf16(__uint_as_float(u2.x), __uint_as_float(u2.y))));
                    if ((c.lane() & 3) < 2) asm volatile("st.shared.b16 [%0], %1;" :: "r"(share + 2048 + c.warp() * 32 + (c.lane() >> 2) * 2 + (c.lane() & 3) * 16),
                                                         "h"((unsigned short)pack_bf16(__uint_as_float(u2.z), 0.f)) : "memory");
                    __syncwarp();
                    if (c.lane() == 0) mbar_arrive(c.zbar() + 40);
                    return true;
                };
                narrow_pass<8, false>(c, q, mma64, nofix, [&]() { if (c.wg() == 0) fetch(); });
                bool shared = true;
                if (c.wg() == 0) { shared = put(); if (!shared) fetch(); }
                fold_mean<false>(c, q, SM_CS, m0, m1);
                TS(5 + c.layer * 16);
                uint4 pq[4];
#pragma unroll
                for (int j = 0; j < 4; j++)
                    pq[j] = make_uint4(pack_bf16(phi(q[8 * j], r0, l0), phi(q[8 * j + 1], r0, l0)), pack_bf16(phi(q[8 * j + 2], r1, l1), phi(q[8 * j + 3], r1, l1)),
                                       pack_bf16(phi(q[8 * j + 4], r0, l0), phi(q[8 * j + 5], r0, l0)), pack_bf16(phi(q[8 * j + 6], r1, l1), phi(q[8 * j + 7], r1, l1)));
                TS(6 + c.layer * 16);
                {
                    const int t = c.lane() & 3;
                    while (!shared) {
                        shared = put();
                        if (!shared) fetch();
                    }
                    mbar_wait(c.zbar() + 40, c.layer);
                    if (c.layer == 1 && c.rw == 0 && c.tid == 0) mbar_arrive(c.zbar() + 8);
                    TS(7 + c.layer * 16);
#pragma unroll
                    for (int h = 0; h < 4; h++) {
                        const uint4 b = ldsm4t(share + h * 512 + c.lane() * 16);
                        uint32_t z0, z1;
                        asm volatile("ld.shared.b32 %0, [%1];" : "=r"(z0) : "r"(share + 2048 + h * 32 + t * 4) : "memory");
                        asm volatile("ld.shared.b32 %0, [%1];" : "=r"(z1) : "r"(share + 2048 + h * 32 + 16 + t * 4) : "memory");
                        float n0[4], n1[4], dn[4];
                        mma16816(n0, pq[h], b.x, b.y);
                        mma16816(n1, pq[h], b.z, b.w);
                        mma16816(dn, pq[h], z0, z1);
                        const float i0 = rcp(dn[0] + 1e-6f), i1 = rcp(dn[2] + 1e-6f);
                        o[h] = make_uint4(pack_bf16(n0[0] * i0, n0[1] * i0), pack_bf16(n0[2] * i1, n0[3] * i1), pack_bf16(n1[0] * i0, n1[1] * i0), pack_bf16(n1[2] * i1, n1[3] * i1));
                    }
                    take_turns(c, O_DELAY);
                    put_lines(c, g_oa + (c.rw * 8 + c.sl) * 512, o, 1);
                    put_hint(c, g_oh + c.rw * 32, c.layer ^ 1);
                }
                TS(8 + c.layer * 16);
            }
            {
                c.fresh();
                float d[32]; uint32_t fix = 0;
                seed_x(xn, d); pin(d);
                {
                    const uint32_t st = (12 + (c.sl >> 1)) % RING;
                    mbar_wait(c.bfull() + st * 8, c.sl >= 6);
                    wg_fence();
#pragma unroll
                    for (int j = 0; j < 4; j++) wgmma_rs_n64(d, o[j], mkdesc(c.sb) + st * 1024 + (c.sl & 1) * 512 + j * 128, 1);
                    wg_commit();
                }
                narrow_pass<12, true>(c, d, mma64, fix, []() {});
                apply_fix(c, d, fix);
                TS(10 + c.layer * 16);
                c.fresh();
                pack_x(d, xn);
                take_turns(c, SRC_DELAY);
                publish_x<0>(c, xn);
                TS(9 + c.layer * 16);
            }
            {
                float m0, m1, r0, r1;
                c.fresh();
                uint32_t fix = 0;
                float d[64], e[24];
                x_pass<16, 0>(c, d, fix, xn, m0, m1, r0, r1);
                TS(12 + c.layer * 16);
                c.fresh();
                if (c.sl & 2) narrow_pass<24, false>(c, e, mma48, fix, []() {});
                apply_fix(c, d, fix);
                fold_mean<true>(c, d, SM_ONES + 1024, m0, m1);
                publish_h<0>(c, d, r0, r1);
                TS(38 + c.layer);
                if (!(c.sl & 2)) narrow_pass<24, false>(c, e, mma48, fix, []() {});
                TS(13 + c.layer * 16);
                c.fresh();
                fold_mean<false>(c, e, SM_CS + 256, m0, m1);
                publish_h<1>(c, e, r0, r1);
            }
            c.fresh();
            ffn2(c, xn);
            TS(34 + c.layer);
            c.fresh();
            if (c.layer == 0) { take_turns(c, SRC_DELAY); publish_x<1>(c, xn); }
        }
        c.fresh();
        const uint32_t tile = c.sb + SM_STG + c.wg() * 8192, srow = tile + (c.warp() * 16 + (c.lane() >> 3)) * 128;
#pragma unroll
        for (int j = 0; j < 4; j++) stsm4(tile_addr(tile, c.warp(), c.lane(), j), xn[j]);
        __syncwarp();
        __nv_bfloat16* dst = out + (size_t)(c.rw * 64 + c.warp() * 16 + (c.lane() >> 3)) * 512 + c.sl * 64 + (c.lane() & 7) * 8;
#pragma unroll
        for (int i = 0; i < 4; i++) {
            uint4 v;
            asm volatile("ld.shared.v4.u32 {%0,%1,%2,%3}, [%4];" : "=r"(v.x), "=r"(v.y), "=r"(v.z), "=r"(v.w)
                         : "r"(srow + i * 512 + (((c.lane() & 7) ^ ((c.lane() >> 3) + 4 * (i & 1))) << 4)) : "memory");
            *reinterpret_cast<uint4*>(dst + i * 4 * 512) = v;
        }
        if (c.lane() == 0) mbar_arrive(c.done());
        TS(40);
        TSG(63);
    }
}

typedef CUresult (*EncodeFn)(CUtensorMap*, CUtensorMapDataType, cuuint32_t, void*, const cuuint64_t*, const cuuint64_t*, const cuuint32_t*, const cuuint32_t*,
                             CUtensorMapInterleave, CUtensorMapSwizzle, CUtensorMapL2promotion, CUtensorMapFloatOOBfill);

void make_map(EncodeFn enc, CUtensorMap* m, const void* p, uint64_t cols, uint64_t rows, uint32_t box_rows) {
    cuuint64_t dims[2] = {cols, rows}, strides[1] = {cols * 2};
    cuuint32_t box[2] = {64, box_rows}, es[2] = {1, 1};
    enc(m, CU_TENSOR_MAP_DATA_TYPE_BFLOAT16, 2, const_cast<void*>(p), dims, strides, box, es, CU_TENSOR_MAP_INTERLEAVE_NONE, CU_TENSOR_MAP_SWIZZLE_128B,
        CU_TENSOR_MAP_L2_PROMOTION_L2_128B, CU_TENSOR_MAP_FLOAT_OOB_FILL_NONE);
}

}

extern "C" void kernel_launch(void* const* d_in, const int* in_sizes, int n_in, void* d_out, int out_size) {
    (void)in_sizes; (void)n_in; (void)out_size;
    static EncodeFn enc = nullptr;
    static int nsm = 0;
    if (!enc) {
        void* fn = nullptr; cudaDriverEntryPointQueryResult qr;
        cudaGetDriverEntryPoint("cuTensorMapEncodeTiled", &fn, cudaEnableDefault, &qr);
        enc = (EncodeFn)fn;
        cudaFuncSetAttribute(fused_kernel, cudaFuncAttributeMaxDynamicSharedMemorySize, SMEM_BYTES);
        int dev = 0; cudaGetDevice(&dev);
        cudaDeviceGetAttribute(&nsm, cudaDevAttrMultiProcessorCount, dev);
    }
    CUtensorMap tx, tq, to, t1, t2, t2b;
    make_map(enc, &tx, d_in[0], 512, 2048, 64);
    make_map(enc, &tq, d_in[1], 1536, 512, 64);
    make_map(enc, &to, d_in[2], 512, 512, 64);
    make_map(enc, &t1, d_in[4], 1376, 512, 64);
    make_map(enc, &t2, d_in[5], 512, 1376, 64);
    make_map(enc, &t2b, d_in[5], 512, 1376, 48);
    fused_kernel<<<nsm == 132 ? 132 : 128, 384, SMEM_BYTES>>>(tx, tq, to, t1, t2, t2b, (const __nv_bfloat16*)d_in[0], (const char*)d_in[1], (const char*)d_in[2], (const char*)d_in[4],
                                                               (const char*)d_in[5], (__nv_bfloat16*)d_out, nsm);
}
```
